```python
import torch

def _softmax(x, axis=-1):
    return torch.softmax(x, dim=axis)
def _gelu(x):
    return torch.nn.functional.gelu(x, approximate="tanh")
def _silu(x):
    return torch.nn.functional.silu(x)
def _sigmoid(x):
    return torch.sigmoid(x)
def _layernorm(x, axis=-1, eps=1e-5):
    m = x.mean(dim=axis, keepdim=True)
    v = x.var(dim=axis, keepdim=True, unbiased=False)
    return (x - m) / torch.sqrt(v + eps)
def _scatter_add(tgt, idx, src, axis=0):
    return tgt.clone().index_add_(axis, idx, src)
def _segment_sum(src, seg, n):
    out = torch.zeros((n,) + src.shape[1:], dtype=src.dtype)
    return out.index_add_(0, seg, src)
def _pad(x, pw):
    flat = tuple(v for pair in reversed(pw) for v in pair)
    return torch.nn.functional.pad(x, flat)

kernel_name = 'standalone__standard_2d_1d_3d_conv__vision'

def setup_inputs():

    _w = (lambda a: (lambda t: t.to(torch.bfloat16) if t.is_floating_point() else t)(torch.as_tensor(a)))
    H = W = 384
    C = 96
    K = 3
    return {
        "x": _w((lambda *s: torch.randn(*s, dtype=torch.bfloat16) * 0.05)(1, H, W, C)),
        "w": _w((lambda *s: torch.randn(*s, dtype=torch.bfloat16) * 0.05)(K, K, C, C)),
        "b": _w((lambda *s: torch.randn(*s, dtype=torch.bfloat16) * 0.05)(C)),
    }

def reference(x, w, b):
    B, H, W, Cin = x.shape
    K = w.shape[0]
    pl = (K - 1) // 2
    pr = K // 2
    xp = _pad(x, ((0, 0), (pl, pr), (pl, pr), (0, 0)))
    out = sum(
        torch.einsum('bhwc,cd->bhwd', xp[:, i:i+H, j:j+W, :], w[i, j])
        for i in range(K) for j in range(K)
    )
    return out + b[None, None, None, :]
```

```cpp
#include <cuda_runtime.h>
#include <cuda.h>
#include <cuda_bf16.h>
#include <stdint.h>

namespace {

constexpr int IMG = 384, CH = 96;
constexpr uint32_t BLK = 3072;
constexpr uint32_t GRP = 3 * BLK;
constexpr uint32_t PLANE = 5760;
constexpr uint32_t STAGE = 2 * PLANE;
constexpr uint32_t ROWP = 576;
constexpr uint32_t OFF_RING = 18 * GRP;
constexpr uint32_t OFF_IN = OFF_RING + 2 * GRP;
constexpr uint32_t OFF_BAR = OFF_IN + 4 * STAGE;
constexpr uint32_t BAR_IN = OFF_BAR;
constexpr uint32_t BAR_RING = OFF_BAR + 32;
constexpr uint32_t BAR_RES = OFF_BAR + 48;
constexpr uint32_t CNT_IN = OFF_BAR + 192;
constexpr uint32_t CNT_RING = OFF_BAR + 208;
constexpr uint32_t OFF_BIAS = OFF_BAR + 256;
constexpr uint32_t SMEM_BYTES = OFF_BIAS + 256;

__device__ __align__(1024) uint8_t g_wprep[24 * GRP];

__device__ __forceinline__ void wg_fence() { asm volatile("wgmma.fence.sync.aligned;" ::: "memory"); }
__device__ __forceinline__ void wg_commit() { asm volatile("wgmma.commit_group.sync.aligned;" ::: "memory"); }
template <int N> __device__ __forceinline__ void wg_wait() { asm volatile("wgmma.wait_group.sync.aligned %0;" ::"n"(N) : "memory"); }

__device__ __forceinline__ void wgmma96(float (&d)[48], uint32_t a0, uint32_t a1, uint32_t a2, uint32_t a3, uint64_t db, int sc) {
  asm volatile(
      "{\n.reg .pred p;\nsetp.ne.b32 p, %53, 0;\n"
      "wgmma.mma_async.sync.aligned.m64n96k16.f32.bf16.bf16 "
      "{%0,%1,%2,%3,%4,%5,%6,%7,%8,%9,%10,%11,%12,%13,%14,%15,%16,%17,%18,%19,%20,%21,%22,%23,"
      "%24,%25,%26,%27,%28,%29,%30,%31,%32,%33,%34,%35,%36,%37,%38,%39,%40,%41,%42,%43,%44,%45,%46,%47},"
      "{%48,%49,%50,%51}, %52, p, 1, 1, 1;\n}\n"
      : "+f"(d[0]), "+f"(d[1]), "+f"(d[2]), "+f"(d[3]), "+f"(d[4]), "+f"(d[5]), "+f"(d[6]), "+f"(d[7]), "+f"(d[8]), "+f"(d[9]),
        "+f"(d[10]), "+f"(d[11]), "+f"(d[12]), "+f"(d[13]), "+f"(d[14]), "+f"(d[15]), "+f"(d[16]), "+f"(d[17]), "+f"(d[18]),
        "+f"(d[19]), "+f"(d[20]), "+f"(d[21]), "+f"(d[22]), "+f"(d[23]), "+f"(d[24]), "+f"(d[25]), "+f"(d[26]), "+f"(d[27]),
        "+f"(d[28]), "+f"(d[29]), "+f"(d[30]), "+f"(d[31]), "+f"(d[32]), "+f"(d[33]), "+f"(d[34]), "+f"(d[35]), "+f"(d[36]),
        "+f"(d[37]), "+f"(d[38]), "+f"(d[39]), "+f"(d[40]), "+f"(d[41]), "+f"(d[42]), "+f"(d[43]), "+f"(d[44]), "+f"(d[45]),
        "+f"(d[46]), "+f"(d[47])
      : "r"(a0), "r"(a1), "r"(a2), "r"(a3), "l"(db), "r"(sc));
}

__device__ __forceinline__ void ldsm4(uint32_t lin, uint32_t* r) {
  uint32_t addr = lin ^ ((lin >> 3) & 0x30u);
  asm volatile("ldmatrix.sync.aligned.m8n8.x4.shared.b16 {%0,%1,%2,%3}, [%4];"
               : "=r"(r[0]), "=r"(r[1]), "=r"(r[2]), "=r"(r[3]) : "r"(addr) : "memory");
}
template <bool SUB> __device__ __forceinline__ uint32_t bop(uint32_t a, uint32_t b) {
  uint32_t r;
  if (SUB) asm volatile("sub.rn.bf16x2 %0, %1, %2;" : "=r"(r) : "r"(a), "r"(b));
  else asm volatile("add.rn.bf16x2 %0, %1, %2;" : "=r"(r) : "r"(a), "r"(b));
  return r;
}
__device__ __forceinline__ void mbar_init(uint32_t bar, uint32_t cnt) { asm volatile("mbarrier.init.shared::cta.b64 [%0], %1;" ::"r"(bar), "r"(cnt) : "memory"); }
__device__ __forceinline__ void mbar_expect(uint32_t bar, uint32_t bytes) {
  asm volatile("mbarrier.arrive.expect_tx.shared::cta.b64 _, [%0], %1;" ::"r"(bar), "r"(bytes) : "memory");
}
__device__ __forceinline__ void mbar_wait(uint32_t bar, uint32_t parity) {
  asm volatile(
      "{\n.reg .pred p, q;\n.reg .u32 n;\n"
      "mov.u32 n, 0;\n"
      "LAB_WAIT:\n"
      "mbarrier.try_wait.parity.shared::cta.b64 p, [%0], %1;\n"
      "@p bra LAB_DONE;\n"
      "add.u32 n, n, 1;\n"
      "setp.lt.u32 q, n, 4000000;\n"
      "@q bra LAB_WAIT;\n"
      "trap;\n"
      "LAB_DONE:\n}\n" ::"r"(bar), "r"(parity) : "memory");
}
__device__ __forceinline__ void tma_in(uint32_t dst, const CUtensorMap* tm, uint32_t bar, int c, int xh, int par, int y) {
  asm volatile("cp.async.bulk.tensor.4d.shared::cluster.global.mbarrier::complete_tx::bytes [%0], [%1, {%3, %4, %5, %6}], [%2];"
               ::"r"(dst), "l"(tm), "r"(bar), "r"(c), "r"(xh), "r"(par), "r"(y) : "memory");
}
__device__ __forceinline__ void bulk_ld(uint32_t dst, const void* src, uint32_t bytes, uint32_t bar) {
  asm volatile("cp.async.bulk.shared::cluster.global.mbarrier::complete_tx::bytes [%0], [%1], %2, [%3];"
               ::"r"(dst), "l"(src), "r"(bytes), "r"(bar) : "memory");
}
__device__ __forceinline__ uint32_t atom_inc(uint32_t addr) {
  uint32_t old;
  asm volatile("atom.acq_rel.cta.shared::cta.add.u32 %0, [%1], 1;" : "=r"(old) : "r"(addr) : "memory");
  return old;
}
__device__ __forceinline__ uint32_t pack2(float lo, float hi) {
  uint32_t r;
  asm("cvt.rn.bf16x2.f32 %0, %1, %2;" : "=r"(r) : "f"(hi), "f"(lo));
  return r;
}

__global__ void prep_kernel(const __nv_bfloat16* __restrict__ w) {
  int t = blockIdx.x * blockDim.x + threadIdx.x;
  if (t >= 3 * 96 * 12) return;
  int u = t % 12, ci = (t / 12) % 96, dx = t / (12 * 96);
  int m = u >> 2, jj = u & 3;
  uint32_t g[3][4];
#pragma unroll
  for (int dy = 0; dy < 3; dy++)
#pragma unroll
    for (int q = 0; q < 4; q++)
      g[dy][q] = *reinterpret_cast<const uint32_t*>(w + ((dy * 3 + dx) * 96 + ci) * 96 + 32 * m + 8 * q + 2 * jj);
  uint32_t u1[4], u2[4];
#pragma unroll
  for (int q = 0; q < 4; q++) {
    float a0 = __uint_as_float(g[0][q] << 16), a1 = __uint_as_float(g[0][q] & 0xffff0000u);
    float b0 = __uint_as_float(g[1][q] << 16), b1 = __uint_as_float(g[1][q] & 0xffff0000u);
    float c0 = __uint_as_float(g[2][q] << 16), c1 = __uint_as_float(g[2][q] & 0xffff0000u);
    float s0 = a0 + c0, s1 = a1 + c1;
    u1[q] = pack2(0.5f * (s0 + b0), 0.5f * (s1 + b1));
    u2[q] = pack2(0.5f * (s0 - b0), 0.5f * (s1 - b1));
  }
  int c = ci >> 4, k = ci & 15;
  uint32_t off = c * 4 * GRP + dx * BLK + m * 1024 + (k >> 3) * 512 + (k & 7) * 64 + ((jj ^ ((k & 7) >> 1)) * 16);
  *reinterpret_cast<uint4*>(g_wprep + off) = make_uint4(g[0][0], g[0][1], g[0][2], g[0][3]);
  *reinterpret_cast<uint4*>(g_wprep + off + GRP) = make_uint4(u1[0], u1[1], u1[2], u1[3]);
  *reinterpret_cast<uint4*>(g_wprep + off + 2 * GRP) = make_uint4(u2[0], u2[1], u2[2], u2[3]);
  *reinterpret_cast<uint4*>(g_wprep + off + 3 * GRP) = make_uint4(g[2][0], g[2][1], g[2][2], g[2][3]);
}

template <bool SUB>
__device__ __forceinline__ void step(float (&acc)[48], const uint32_t* a, const uint32_t* b, uint64_t db, int sc, uint32_t lin, uint32_t* dst) {
  uint32_t p[4], q[4];
  wg_wait<2>();
#pragma unroll
  for (int i = 0; i < 4; i++) p[i] = bop<SUB>(a[i], b[i]);
  wg_fence();
  wgmma96(acc, p[0], p[1], p[2], p[3], db, sc);
  wg_commit();
  ldsm4(lin, dst);
  wg_wait<2>();
#pragma unroll
  for (int i = 0; i < 4; i++) q[i] = bop<SUB>(a[4 + i], b[4 + i]);
  wg_fence();
  wgmma96(acc, q[0], q[1], q[2], q[3], db + ((2 * BLK) >> 4), 1);
  wg_commit();
  ldsm4(lin + 64, dst + 4);
  wg_wait<2>();
  wg_fence();
  wgmma96(acc, p[1], q[0], p[3], q[2], db + (BLK >> 4), 1);
  wg_commit();
}

__global__ void __launch_bounds__(256, 1)
conv_kernel(const __grid_constant__ CUtensorMap tmx, const __nv_bfloat16* __restrict__ bias, __nv_bfloat16* __restrict__ out) {
  extern __shared__ __align__(1024) uint8_t smem[];
  const uint32_t sb = (uint32_t)__cvta_generic_to_shared(smem);
  const int tid = threadIdx.x;
  const int warp = __shfl_sync(0xffffffffu, tid >> 5, 0);
  const int wg = warp >> 2, wi = warp & 3, lane = tid & 31;
  const int tile_x = (blockIdx.x & 7) * 48, tile_y = (blockIdx.x >> 3) * 24;

  if (tid == 0) {
    for (int i = 0; i < 24; i++) mbar_init(sb + OFF_BAR + i * 8, 1);
    for (int i = 0; i < 6; i++) *reinterpret_cast<uint32_t*>(smem + CNT_IN + i * 4) = 0;
    asm volatile("fence.mbarrier_init.release.cluster;" ::: "memory");
  }
  if (tid >= 64 && tid < 64 + 48) reinterpret_cast<uint32_t*>(smem + OFF_BIAS)[tid - 64] = reinterpret_cast<const uint32_t*>(bias)[tid - 64];
  __syncthreads();

  const int nunits = 5 - wg;
  const int nstages = 3 * nunits;
  const uint32_t inbase = sb + OFF_IN + wg * 2 * STAGE;
  const uint32_t barin = sb + BAR_IN + wg * 16;
  int lux = wg, luy = 0, lcp = wg, lpos = 0;
  auto issue_stage = [&](int buf, int ux, int uy, int cp) {
    uint32_t bar = barin + buf * 8, dst = inbase + buf * STAGE;
    int xh = (tile_x + ux * 16) >> 1, y = tile_y + uy * 8 - 1;
    mbar_expect(bar, STAGE);
    tma_in(dst, &tmx, bar, cp * 32, xh - 1, 1, y);
    tma_in(dst + PLANE, &tmx, bar, cp * 32, xh, 0, y);
  };
  auto advance_load = [&]() {
    lcp = (lcp == 2) ? 0 : lcp + 1;
    if (++lpos == 3) { lpos = 0; lux += 2; if (lux >= 3) { lux -= 3; luy++; } }
  };
  if (wi == 0 && lane == 0) issue_stage(0, lux, luy, lcp);
  advance_load();
  if (tid == 32) {
    for (int c = 0; c < 6; c++) {
      for (int k = 0; k < 3; k++) {
        uint32_t bar = sb + BAR_RES + (c * 3 + k) * 8;
        mbar_expect(bar, GRP);
        bulk_ld(sb + (c * 3 + k) * GRP, g_wprep + (c * 4 + k) * GRP, GRP, bar);
      }
      if (c < 2) {
        mbar_expect(sb + BAR_RING + c * 8, GRP);
        bulk_ld(sb + OFF_RING + c * GRP, g_wprep + (c * 4 + 3) * GRP, GRP, sb + BAR_RING + c * 8);
      }
    }
  }
  if (wi == 0 && lane == 0) issue_stage(1, lux, luy, lcp);
  advance_load();
  __syncwarp();

  const uint32_t lin0 = inbase + (((lane >> 3) & 1) ? PLANE : 0) + wi * 2 * ROWP + (lane & 7) * 64 + (lane >> 4) * 16;
  const uint64_t dconst = ((uint64_t)(1024 >> 4) << 16) | ((uint64_t)(512 >> 4) << 32) | ((uint64_t)2 << 62);
  const uint64_t dres = dconst | (uint64_t)((sb & 0x3FFFF) >> 4);
  const uint64_t dring = dconst | (uint64_t)(((sb + OFF_RING) & 0x3FFFF) >> 4);

  int ux = wg, uy = 0, cp = wg, pos = 0;
  int tpair = wg;

  auto ring_release = [&](int tp, int cc, int cpair) {
    if (lane == 0) {
      uint32_t old = atom_inc(sb + CNT_RING + cc * 4);
      uint32_t target = (tp <= 12) ? (8 * tp + 8) : (56 + 4 * tp);
      if (old + 1 == target && tp < 14) {
        int cn = (cpair == 2) ? 0 : cpair + 1;
        uint32_t bar = sb + BAR_RING + cc * 8;
        mbar_expect(bar, GRP);
        bulk_ld(sb + OFF_RING + cc * GRP, g_wprep + (uint32_t)(((cn * 2 + cc) * 4 + 3) * GRP), GRP, bar);
      }
    }
    __syncwarp();
  };

  if (wg == 1) {
    mbar_wait(sb + BAR_RING, 0);
    ring_release(0, 0, 0);
    mbar_wait(sb + BAR_RING + 8, 0);
    ring_release(0, 1, 0);
  }
  float acc[4][48];
  uint32_t A[8], B[8], C[8];
  mbar_wait(barin, 0);
  ldsm4(lin0, A); ldsm4(lin0 + 64, A + 4);
  ldsm4(lin0 + 2 * ROWP, B); ldsm4(lin0 + 2 * ROWP + 64, B + 4);

  for (int s = 0; s < nstages; s++) {
    const int buf = s & 1;
    const uint32_t cur = lin0 + buf * STAGE, nxt = lin0 + (buf ^ 1) * STAGE;
    const int sc = (pos != 0);
    const uint64_t db = dres + (uint64_t)((cp * 6 * GRP) >> 4);
    const uint32_t bres = sb + BAR_RES + cp * 48;
    mbar_wait(bres, 0);
    step<true>(acc[0], A, B, db, sc, cur + ROWP, C);
    mbar_wait(bres + 8, 0);
    if (pos != 0) ring_release(tpair - 1, 1, cp == 0 ? 2 : cp - 1);
    step<false>(acc[1], C, B, db + (GRP >> 4), sc, cur + 3 * ROWP, A);
    mbar_wait(bres + 16, 0);
    step<true>(acc[2], B, C, db + ((2 * GRP) >> 4), sc, cur + 2 * ROWP + 32, B);
    mbar_wait(sb + BAR_RING, tpair & 1);
    step<true>(acc[3], A, C, dring, sc, cur + 32, A);
    mbar_wait(bres + 24, 0);
    step<true>(acc[0], A, B, db + ((3 * GRP) >> 4), 1, cur + ROWP + 32, C);
    mbar_wait(bres + 32, 0);
    ring_release(tpair, 0, cp);
    step<false>(acc[1], C, B, db + ((4 * GRP) >> 4), 1, cur + 3 * ROWP + 32, A);
    mbar_wait(bres + 40, 0);
    if (s + 1 < nstages) mbar_wait(barin + (buf ^ 1) * 8, ((s + 1) >> 1) & 1);
    if (lane == 0) {
      uint32_t old = atom_inc(sb + CNT_IN + wg * 8 + buf * 4);
      if ((old & 3) == 3 && s + 2 < nstages) issue_stage(buf, lux, luy, lcp);
    }
    __syncwarp();
    advance_load();
    step<true>(acc[2], B, C, db + ((5 * GRP) >> 4), 1, nxt + 2 * ROWP, B);
    mbar_wait(sb + BAR_RING + 8, tpair & 1);
    step<true>(acc[3], A, C, dring + (GRP >> 4), 1, nxt, A);

    if (pos == 2) {
      wg_wait<0>();
      ring_release(tpair, 1, cp);
#pragma unroll
      for (int i = 0; i < 4; i++)
#pragma unroll
        for (int j = 0; j < 48; j++) asm volatile("" : "+f"(acc[i][j])::"memory");
      const uint32_t ooff = (uint32_t)(((tile_y + uy * 8 + wi * 2) * IMG + tile_x + ux * 16 + 2 * (lane >> 2)) * (CH * 2) + (lane & 3) * 16);
      uint8_t* op = reinterpret_cast<uint8_t*>(out) + ooff;
#pragma unroll
      for (int m = 0; m < 3; m++) {
        uint32_t bb[4];
        asm volatile("ld.shared.v4.u32 {%0,%1,%2,%3}, [%4];" : "=r"(bb[0]), "=r"(bb[1]), "=r"(bb[2]), "=r"(bb[3]) : "r"(sb + OFF_BIAS + m * 64 + (lane & 3) * 16));
#pragma unroll
        for (int h = 0; h < 2; h++) {
          uint32_t y0[4], y1[4];
#pragma unroll
          for (int jj = 0; jj < 4; jj++) {
            const int i0 = 4 * (4 * m + jj) + 2 * h;
            float t0 = acc[1][i0] + __uint_as_float(bb[jj] << 16);
            float t1 = acc[1][i0 + 1] + __uint_as_float(bb[jj] & 0xffff0000u);
            y0[jj] = pack2(t0 + acc[2][i0] + acc[0][i0], t1 + acc[2][i0 + 1] + acc[0][i0 + 1]);
            y1[jj] = pack2(t0 - acc[2][i0] + acc[3][i0], t1 - acc[2][i0 + 1] + acc[3][i0 + 1]);
          }
          asm volatile("st.global.v4.u32 [%0], {%1,%2,%3,%4};" ::"l"(op + h * 192 + m * 64), "r"(y0[0]), "r"(y0[1]), "r"(y0[2]), "r"(y0[3]) : "memory");
          asm volatile("st.global.v4.u32 [%0], {%1,%2,%3,%4};" ::"l"(op + IMG * CH * 2 + h * 192 + m * 64), "r"(y1[0]), "r"(y1[1]), "r"(y1[2]), "r"(y1[3]) : "memory");
        }
      }
      pos = 0;
      ux += 2;
      if (ux >= 3) { ux -= 3; uy++; }
    } else {
      pos++;
    }
    cp = (cp == 2) ? 0 : cp + 1;
    tpair++;
  }
}

typedef CUresult (*EncodeFn)(CUtensorMap*, CUtensorMapDataType, cuuint32_t, void*, const cuuint64_t*, const cuuint64_t*, const cuuint32_t*,
                             const cuuint32_t*, CUtensorMapInterleave, CUtensorMapSwizzle, CUtensorMapL2promotion, CUtensorMapFloatOOBfill);

}

extern "C" void kernel_launch(void* const* d_in, const int* in_sizes, int n_in, void* d_out, int out_size) {
  const __nv_bfloat16* x = (const __nv_bfloat16*)d_in[0];
  const __nv_bfloat16* w = (const __nv_bfloat16*)d_in[1];
  const __nv_bfloat16* b = (const __nv_bfloat16*)d_in[2];
  __nv_bfloat16* out = (__nv_bfloat16*)d_out;

  static EncodeFn enc = nullptr;
  if (!enc) {
    cudaDriverEntryPointQueryResult qr;
    cudaGetDriverEntryPoint("cuTensorMapEncodeTiled", (void**)&enc, cudaEnableDefault, &qr);
    cudaFuncSetAttribute(conv_kernel, cudaFuncAttributeMaxDynamicSharedMemorySize, SMEM_BYTES);
  }
  CUtensorMap tmx;
  cuuint64_t dims[4] = {(cuuint64_t)CH, (cuuint64_t)(IMG / 2), 2, (cuuint64_t)IMG};
  cuuint64_t strides[3] = {(cuuint64_t)CH * 4, (cuuint64_t)CH * 2, (cuuint64_t)IMG * CH * 2};
  cuuint32_t box[4] = {32, 9, 1, 10};
  cuuint32_t es[4] = {1, 1, 1, 1};
  enc(&tmx, CU_TENSOR_MAP_DATA_TYPE_BFLOAT16, 4, (void*)x, dims, strides, box, es, CU_TENSOR_MAP_INTERLEAVE_NONE,
      CU_TENSOR_MAP_SWIZZLE_64B, CU_TENSOR_MAP_L2_PROMOTION_L2_128B, CU_TENSOR_MAP_FLOAT_OOB_FILL_NONE);

  prep_kernel<<<27, 128>>>(w);
  conv_kernel<<<128, 256, SMEM_BYTES>>>(tmx, b, out);
}
```

```cpp
#include <cuda_runtime.h>
#include <cuda.h>
#include <cuda_bf16.h>
#include <stdint.h>

namespace {

constexpr int IMG = 384, CH = 96;
#define PF0 1
#define PF1 1
#define PFU0 99
#define PFU1 99
#define PFU2 99
#define S1POS 1
#define S2POS 3
constexpr int WD = 3;
constexpr uint32_t BLK = 3072;
constexpr uint32_t GRP = 3 * BLK;
constexpr uint32_t PLANE = 5760;
constexpr uint32_t STAGE = 2 * PLANE;
constexpr uint32_t ROWP = 576;
constexpr uint32_t OFF_RING = 18 * GRP;
constexpr uint32_t OFF_IN = OFF_RING + 3 * GRP;
constexpr uint32_t OFF_BAR = OFF_IN + 3 * STAGE;
constexpr uint32_t BAR_INF = OFF_BAR;
constexpr uint32_t BAR_WF = OFF_BAR + 24;
constexpr uint32_t BAR_RES = OFF_BAR + 48;
constexpr uint32_t BAR_INE = OFF_BAR + 96;
constexpr uint32_t BAR_WE = OFF_BAR + 112;
constexpr uint32_t BAR_BIAS = OFF_BAR + 160;
constexpr uint32_t OFF_BIAS = OFF_BAR + 256;
constexpr uint32_t OFF_TR = OFF_BIAS + 256;
constexpr uint32_t SMEM_BYTES = OFF_TR;

constexpr uint32_t OFF_SYNC = 24 * GRP;
__device__ __align__(1024) uint8_t g_wprep[OFF_SYNC + 1024];

__device__ __forceinline__ void wg_fence() { asm volatile("wgmma.fence.sync.aligned;" ::: "memory"); }
__device__ __forceinline__ void wg_commit() { asm volatile("wgmma.commit_group.sync.aligned;" ::: "memory"); }
__device__ __forceinline__ void sfence() { asm volatile("pmevent 0;" ::: "memory"); }
template <int N> __device__ __forceinline__ void wg_wait() { asm volatile("wgmma.wait_group.sync.aligned %0;" ::"n"(N) : "memory"); }

__device__ __forceinline__ void wgmma96(float (&d)[48], uint32_t a0, uint32_t a1, uint32_t a2, uint32_t a3, uint64_t db, int sc) {
  asm volatile(
      "{\n.reg .pred p;\nsetp.ne.b32 p, %53, 0;\n"
      "wgmma.mma_async.sync.aligned.m64n96k16.f32.bf16.bf16 "
      "{%0,%1,%2,%3,%4,%5,%6,%7,%8,%9,%10,%11,%12,%13,%14,%15,%16,%17,%18,%19,%20,%21,%22,%23,"
      "%24,%25,%26,%27,%28,%29,%30,%31,%32,%33,%34,%35,%36,%37,%38,%39,%40,%41,%42,%43,%44,%45,%46,%47},"
      "{%48,%49,%50,%51}, %52, p, 1, 1, 1;\n}\n"
      : "+f"(d[0]), "+f"(d[1]), "+f"(d[2]), "+f"(d[3]), "+f"(d[4]), "+f"(d[5]), "+f"(d[6]), "+f"(d[7]), "+f"(d[8]), "+f"(d[9]),
        "+f"(d[10]), "+f"(d[11]), "+f"(d[12]), "+f"(d[13]), "+f"(d[14]), "+f"(d[15]), "+f"(d[16]), "+f"(d[17]), "+f"(d[18]),
        "+f"(d[19]), "+f"(d[20]), "+f"(d[21]), "+f"(d[22]), "+f"(d[23]), "+f"(d[24]), "+f"(d[25]), "+f"(d[26]), "+f"(d[27]),
        "+f"(d[28]), "+f"(d[29]), "+f"(d[30]), "+f"(d[31]), "+f"(d[32]), "+f"(d[33]), "+f"(d[34]), "+f"(d[35]), "+f"(d[36]),
        "+f"(d[37]), "+f"(d[38]), "+f"(d[39]), "+f"(d[40]), "+f"(d[41]), "+f"(d[42]), "+f"(d[43]), "+f"(d[44]), "+f"(d[45]),
        "+f"(d[46]), "+f"(d[47])
      : "r"(a0), "r"(a1), "r"(a2), "r"(a3), "l"(db), "r"(sc));
}

__device__ __forceinline__ void ldsm4(uint32_t addr, uint32_t* r) {
  asm volatile("ldmatrix.sync.aligned.m8n8.x4.shared.b16 {%0,%1,%2,%3}, [%4];"
               : "=r"(r[0]), "=r"(r[1]), "=r"(r[2]), "=r"(r[3]) : "r"(addr) : "memory");
}
__device__ __forceinline__ uint32_t vxor32(uint32_t a) {
  uint32_t r;
  asm volatile("xor.b32 %0, %1, 32;" : "=r"(r) : "r"(a));
  return r;
}
__device__ __forceinline__ float fadd(float a, float b) { float r; asm volatile("add.rn.f32 %0, %1, %2;" : "=f"(r) : "f"(a), "f"(b)); return r; }
__device__ __forceinline__ float fsub(float a, float b) { float r; asm volatile("sub.rn.f32 %0, %1, %2;" : "=f"(r) : "f"(a), "f"(b)); return r; }
__device__ __forceinline__ float vlo(uint32_t v) { uint32_t r; asm volatile("shl.b32 %0, %1, 16;" : "=r"(r) : "r"(v)); return __uint_as_float(r); }
__device__ __forceinline__ float vhi(uint32_t v) { uint32_t r; asm volatile("and.b32 %0, %1, 0xffff0000;" : "=r"(r) : "r"(v)); return __uint_as_float(r); }
__device__ __forceinline__ void lds128(uint32_t addr, uint32_t (&r)[4]) {
  asm volatile("ld.shared.v4.u32 {%0,%1,%2,%3}, [%4];" : "=r"(r[0]), "=r"(r[1]), "=r"(r[2]), "=r"(r[3]) : "r"(addr) : "memory");
}
template <bool SUB> __device__ __forceinline__ uint32_t bop(uint32_t a, uint32_t b) {
  uint32_t r;
  if (SUB) asm volatile("sub.rn.bf16x2 %0, %1, %2;" : "=r"(r) : "r"(a), "r"(b));
  else asm volatile("add.rn.bf16x2 %0, %1, %2;" : "=r"(r) : "r"(a), "r"(b));
  return r;
}
__device__ __forceinline__ void mbar_init(uint32_t bar, uint32_t cnt) { asm volatile("mbarrier.init.shared::cta.b64 [%0], %1;" ::"r"(bar), "r"(cnt) : "memory"); }
__device__ __forceinline__ void mbar_expect(uint32_t bar, uint32_t bytes) {
  asm volatile("mbarrier.arrive.expect_tx.shared::cta.b64 _, [%0], %1;" ::"r"(bar), "r"(bytes) : "memory");
}
__device__ __forceinline__ void mbar_wait(uint32_t bar, uint32_t parity) {
  asm volatile(
      "{\n.reg .pred p, q;\n.reg .u32 n;\n"
      "mov.u32 n, 0;\n"
      "LAB_WAIT:\n"
      "mbarrier.try_wait.parity.shared::cta.b64 p, [%0], %1;\n"
      "@p bra LAB_DONE;\n"
      "add.u32 n, n, 1;\n"
      "setp.lt.u32 q, n, 4000000;\n"
      "@q bra LAB_WAIT;\n"
      "trap;\n"
      "LAB_DONE:\n}\n" ::"r"(bar), "r"(parity) : "memory");
}
__device__ __forceinline__ void tma_in(uint32_t dst, const CUtensorMap* tm, uint32_t bar, int c, int xh, int par, int y) {
  asm volatile("cp.async.bulk.tensor.4d.shared::cluster.global.mbarrier::complete_tx::bytes [%0], [%1, {%3, %4, %5, %6}], [%2];"
               ::"r"(dst), "l"(tm), "r"(bar), "r"(c), "r"(xh), "r"(par), "r"(y) : "memory");
}
__device__ __forceinline__ void bulk_ld(uint32_t dst, const void* src, uint32_t bytes, uint32_t bar) {
  asm volatile("cp.async.bulk.shared::cluster.global.mbarrier::complete_tx::bytes [%0], [%1], %2, [%3];"
               ::"r"(dst), "l"(src), "r"(bytes), "r"(bar) : "memory");
}
__device__ __forceinline__ void tma_stage_p(uint32_t v, uint32_t want, uint32_t dst, const CUtensorMap* tm, uint32_t bar, int c, int xh, int y) {
  asm volatile("{\n.reg .pred p, e;\nelect.sync _|e, 0xffffffff;\nsetp.eq.and.u32 p, %8, %9, e;\n"
               "@p mbarrier.arrive.expect_tx.shared::cta.b64 _, [%3], %10;\n"
               "@p cp.async.bulk.tensor.4d.shared::cluster.global.mbarrier::complete_tx::bytes [%0], [%2, {%4, %5, 1, %7}], [%3];\n"
               "@p cp.async.bulk.tensor.4d.shared::cluster.global.mbarrier::complete_tx::bytes [%1], [%2, {%4, %6, 0, %7}], [%3];\n}\n"
               ::"r"(dst), "r"(dst + PLANE), "l"(tm), "r"(bar), "r"(c), "r"(xh - 1), "r"(xh), "r"(y), "r"(v), "r"(want), "n"(STAGE) : "memory");
}
template <uint32_t BYTES>
__device__ __forceinline__ void bulk_ld_p(uint32_t v, uint32_t want, uint32_t dst, const void* src, uint32_t bar) {
  asm volatile("{\n.reg .pred p, e;\nelect.sync _|e, 0xffffffff;\nsetp.eq.and.u32 p, %3, %4, e;\n"
               "@p mbarrier.arrive.expect_tx.shared::cta.b64 _, [%2], %5;\n"
               "@p cp.async.bulk.shared::cluster.global.mbarrier::complete_tx::bytes [%0], [%1], %5, [%2];\n}\n"
               ::"r"(dst), "l"(src), "r"(bar), "r"(v), "r"(want), "n"(BYTES) : "memory");
}
__device__ __forceinline__ void tma_stage_e(uint32_t dst, const CUtensorMap* tm, uint32_t bar, int c, int xh, int y) {
  asm volatile("{\n.reg .pred p;\nelect.sync _|p, 0xffffffff;\n"
               "@p mbarrier.arrive.expect_tx.shared::cta.b64 _, [%3], %8;\n"
               "@p cp.async.bulk.tensor.4d.shared::cluster.global.mbarrier::complete_tx::bytes [%0], [%2, {%4, %5, 1, %7}], [%3];\n"
               "@p cp.async.bulk.tensor.4d.shared::cluster.global.mbarrier::complete_tx::bytes [%1], [%2, {%4, %6, 0, %7}], [%3];\n}\n"
               ::"r"(dst), "r"(dst + PLANE), "l"(tm), "r"(bar), "r"(c), "r"(xh - 1), "r"(xh), "r"(y), "n"(STAGE) : "memory");
}
template <uint32_t BYTES>
__device__ __forceinline__ void bulk_ld_e(uint32_t dst, const void* src, uint32_t bar) {
  asm volatile("{\n.reg .pred p;\nelect.sync _|p, 0xffffffff;\n"
               "@p mbarrier.arrive.expect_tx.shared::cta.b64 _, [%2], %3;\n"
               "@p cp.async.bulk.shared::cluster.global.mbarrier::complete_tx::bytes [%0], [%1], %3, [%2];\n}\n"
               ::"r"(dst), "l"(src), "r"(bar), "n"(BYTES) : "memory");
}
__device__ __forceinline__ void mbar_arrive1(uint32_t bar) {
  asm volatile("{\n.reg .pred e;\nelect.sync _|e, 0xffffffff;\n@e mbarrier.arrive.shared::cta.b64 _, [%0];\n}\n" ::"r"(bar) : "memory");
}
__device__ __forceinline__ bool elect_one() {
  uint32_t r;
  asm volatile("{\n.reg .pred p;\nelect.sync _|p, 0xffffffff;\nselp.u32 %0, 1, 0, p;\n}\n" : "=r"(r));
  return r;
}
__device__ __forceinline__ bool mbar_test(uint32_t bar, uint32_t parity) {
  uint32_t r;
  asm volatile("{\n.reg .pred p;\nmbarrier.test_wait.parity.shared::cta.b64 p, [%1], %2;\nselp.u32 %0, 1, 0, p;\n}\n" : "=r"(r) : "r"(bar), "r"(parity) : "memory");
  return r;
}
#define TS(i)
#define TC(i)
#define TR(i)
#define TRA(i)
#define TRG(i)
__device__ __forceinline__ uint32_t pack2(float lo, float hi) {
  uint32_t r;
  asm volatile("cvt.rn.bf16x2.f32 %0, %1, %2;" : "=r"(r) : "f"(hi), "f"(lo));
  return r;
}

__device__ __forceinline__ void prep_item(const __nv_bfloat16* __restrict__ w, uint8_t* wprep, int item, int lane) {
  const int m = item % 3, dx = (item / 3) % 3, ci = (item / 9) * 8 + (lane >> 2), jj = lane & 3;
  uint32_t g[3][4];
#pragma unroll
  for (int dy = 0; dy < 3; dy++)
#pragma unroll
    for (int q = 0; q < 4; q++)
      g[dy][q] = *reinterpret_cast<const uint32_t*>(w + ((dy * 3 + dx) * 96 + ci) * 96 + 32 * m + 8 * q + 2 * jj);
  uint32_t u1[4], u2[4];
#pragma unroll
  for (int q = 0; q < 4; q++) {
    float a0 = __uint_as_float(g[0][q] << 16), a1 = __uint_as_float(g[0][q] & 0xffff0000u);
    float b0 = __uint_as_float(g[1][q] << 16), b1 = __uint_as_float(g[1][q] & 0xffff0000u);
    float c0 = __uint_as_float(g[2][q] << 16), c1 = __uint_as_float(g[2][q] & 0xffff0000u);
    float s0 = a0 + c0, s1 = a1 + c1;
    u1[q] = pack2(0.5f * (s0 + b0), 0.5f * (s1 + b1));
    u2[q] = pack2(0.5f * (s0 - b0), 0.5f * (s1 - b1));
  }
  int c = ci >> 4, k = ci & 15;
  uint32_t off = dx * BLK + m * 1024 + (k >> 3) * 512 + (k & 7) * 64 + ((jj ^ ((k & 7) >> 1)) * 16);
  uint8_t* res = wprep + c * 3 * GRP + off;
  *reinterpret_cast<uint4*>(res) = make_uint4(g[0][0], g[0][1], g[0][2], g[0][3]);
  *reinterpret_cast<uint4*>(res + GRP) = make_uint4(u1[0], u1[1], u1[2], u1[3]);
  *reinterpret_cast<uint4*>(res + 2 * GRP) = make_uint4(u2[0], u2[1], u2[2], u2[3]);
  *reinterpret_cast<uint4*>(wprep + OFF_RING + c * GRP + off) = make_uint4(g[2][0], g[2][1], g[2][2], g[2][3]);
}

template <bool SUB, int SC, class H0, class H1, class H2, class H3>
__device__ __forceinline__ void step(float (&acc)[48], const uint32_t* a, const uint32_t* b, uint64_t db, H0 h0, H1 h1, H2 h2, H3 h3) {
  uint32_t p[4], q[4];
  wg_wait<WD>();
  h0();
#pragma unroll
  for (int i = 0; i < 4; i++) p[i] = bop<SUB>(a[i], b[i]);
  wg_fence();
  wgmma96(acc, p[0], p[1], p[2], p[3], db, SC);
  wg_commit();
  h1();
  sfence();
  wg_wait<WD>();
#pragma unroll
  for (int i = 0; i < 4; i++) q[i] = bop<SUB>(a[4 + i], b[4 + i]);
  wg_fence();
  wgmma96(acc, q[0], q[1], q[2], q[3], db + ((2 * BLK) >> 4), 1);
  wg_commit();
  h2();
  wg_wait<WD>();
  wg_fence();
  wgmma96(acc, p[1], q[0], p[3], q[2], db + (BLK >> 4), 1);
  wg_commit();
  h3();
  sfence();
}

struct Ctx {
  uint32_t sb;
  uint64_t dres;
  int wg;
  bool first;
};

template <int CK, int R, int J>
__device__ __forceinline__ void ldraw(const uint32_t (&AD)[4], uint32_t* dst) {
  constexpr int N = R + J;
  constexpr bool X = (((CK & 1) ^ (CK >> 1) ^ (N >> 2)) & 1) != 0;
  constexpr uint32_t OFF = (CK >> 1) * STAGE + R * 512 + (N >> 2) * 256;
  if (CK < 6) ldsm4((X ? vxor32(AD[N & 3]) : AD[N & 3]) + OFF, dst + 4 * J);
}

template <int CK>
__device__ __forceinline__ void chunk(const Ctx& cx, float (&acc)[4][48], uint32_t (&D0)[8], uint32_t (&D1)[8], uint32_t (&D2)[8], const uint32_t (&AD)[4]) {
  constexpr int P = CK >> 1, CC = CK & 1;
  constexpr int SC = CK != 0;
  const uint32_t sb = cx.sb;
  const uint64_t db = cx.dres + (uint64_t)((CK * 3 * GRP) >> 4);
  const uint64_t dr = cx.dres + (uint64_t)((OFF_RING + (CK % 3) * GRP) >> 4);
  auto nop = []() {};
  uint32_t D3[8];
  bool okw = true, oki = true;
  auto test = [&]() {
    okw = mbar_test(sb + BAR_WF + (CK % 3) * 8, CK / 3);
    if (CC == 0 && P < 2) oki = mbar_test(sb + BAR_INF + (P + 1) * 8, cx.wg);
  };
  auto check = [&]() {
    if (!(okw && oki) || cx.first) {
      if (!okw) mbar_wait(sb + BAR_WF + (CK % 3) * 8, CK / 3);
      if (CC == 0 && P < 2 && !oki) mbar_wait(sb + BAR_INF + (P + 1) * 8, cx.wg);
      if (CK != 5 && cx.first) mbar_wait(sb + BAR_RES + (CK + 1) * 8, 0);
    }
  };
  step<true, SC>(acc[0], D0, D2, db, nop, [&]() { ldraw<CK, 1, 1>(AD, D1); }, [&]() { if (CK == 5) test(); }, [&]() { ldraw<CK, 3, 0>(AD, D3); });
  if (CK == 5) check();
  step<false, 1>(acc[1], D1, D2, db + (GRP >> 4), [&]() { if (CK != 0) mbar_arrive1(sb + BAR_WE - 8 + CK * 8); },
                 [&]() { ldraw<CK, 3, 1>(AD, D3); }, [&]() { if (CC == 1 && P < 2) mbar_arrive1(sb + BAR_INE + P * 8); },
                 [&]() { ldraw<CK + 1, 0, 0>(AD, D0); });
  step<true, SC>(acc[2], D2, D1, db + ((2 * GRP) >> 4), nop, [&]() { ldraw<CK + 1, 2, 0>(AD, D2); }, [&]() { if (CK != 5) test(); },
                 [&]() { ldraw<CK + 1, 2, 1>(AD, D2); });
  if (CK != 5) check();
  step<true, SC>(acc[3], D3, D1, dr, nop, [&]() { ldraw<CK + 1, 0, 1>(AD, D0); }, nop, [&]() { ldraw<CK + 1, 1, 0>(AD, D1); });
}

template <int M, int H, int ROW, bool PACE>
__device__ __forceinline__ void piece(float (&acc)[4][48], const uint32_t (&bb)[4], uint8_t* op, bool st) {
  uint32_t y[4];
#pragma unroll
  for (int jj = 0; jj < 4; jj++) {
    const int i0 = 4 * (4 * M + jj) + 2 * H;
    float v0, v1;
    if (ROW == 0) {
      v0 = fadd(acc[0][i0], acc[1][i0]);
      if (PACE && PF0 >= 2) sfence();
      v0 = fadd(v0, acc[2][i0]);
      if (PACE && PF0 >= 1) sfence();
      v1 = fadd(acc[0][i0 + 1], acc[1][i0 + 1]);
      if (PACE && PF0 >= 3) sfence();
      v1 = fadd(v1, acc[2][i0 + 1]);
    } else {
      v0 = fsub(fadd(acc[3][i0], acc[1][i0]), acc[2][i0]);
      if (PACE && PF1 >= 2) sfence();
      if (PACE) acc[1][i0] = vlo(bb[jj]);
      if (PACE && PF1 >= 1) sfence();
      v1 = fsub(fadd(acc[3][i0 + 1], acc[1][i0 + 1]), acc[2][i0 + 1]);
      if (PACE && PF1 >= 3) sfence();
      if (PACE) acc[1][i0 + 1] = vhi(bb[jj]);
    }
    y[jj] = pack2(v0, v1);
    if (PACE) sfence();
  }
  asm volatile("{\n.reg .pred p;\nsetp.ne.u32 p, %5, 0;\n@p st.global.L1::no_allocate.v4.u32 [%0], {%1,%2,%3,%4};\n}\n" ::"l"(op + ROW * IMG * CH * 2 + H * 192 + M * 64),
               "r"(y[0]), "r"(y[1]), "r"(y[2]), "r"(y[3]), "r"((uint32_t)st) : "memory");
}

__global__ void __launch_bounds__(256, 1)
conv_kernel(const __grid_constant__ CUtensorMap tmx, const __grid_constant__ CUtensorMap tmx0, uint8_t* wprep, const uint8_t* __restrict__ xin, const __nv_bfloat16* __restrict__ w, const __nv_bfloat16* __restrict__ bias, __nv_bfloat16* __restrict__ out) {
  extern __shared__ __align__(1024) uint8_t smem[];
  const uint32_t sb = (uint32_t)__cvta_generic_to_shared(smem);
  const int tid = threadIdx.x;
  const int warp = __shfl_sync(0xffffffffu, tid >> 5, 0);
  const int wg = warp >> 2, wi = warp & 3, lane = tid & 31;
  const int tile_x = (blockIdx.x & 7) * 48, tile_y = (blockIdx.x >> 3) * 24;

  TRG(0); TR(1);
  auto pf_unit = [&](int x0, int y0, int r0, int rstep, int n) {
#pragma unroll
    for (int i = 0; i < n; i++) {
      const int r = r0 + rstep * i;
      const int off = ((((y0 - 1 + r) * IMG + x0 - 1) * (CH * 2)) & ~127) + lane * 128;
      if (r < 10 && lane < 28 && off >= 0) asm volatile("prefetch.global.L2 [%0];" ::"l"(xin + (uint32_t)off) : "memory");
    }
  };
  if (warp == 5) {
    if (blockIdx.x < 108) {
      prep_item(w, wprep, blockIdx.x, lane);
      asm volatile("fence.proxy.async.global;" ::: "memory");
      __syncwarp();
      TRA(83);
      asm volatile("{\n.reg .pred e;\nelect.sync _|e, 0xffffffff;\n@e red.release.gpu.global.inc.u32 [%0], 0xffffffff;\n}\n" ::"l"(wprep + OFF_SYNC + (blockIdx.x & 3) * 128) : "memory");
      TRA(84);
    }
  } else if (warp == 4) {
    if (lane == 0) {
#pragma unroll
      for (int i = 0; i < 21; i++) mbar_init(sb + OFF_BAR + i * 8, (i < 12 || i == 20) ? 1 : 4);
      asm volatile("fence.mbarrier_init.release.cluster;" ::: "memory");
    }
    __syncwarp();
    asm volatile("bar.arrive 1, 160;" ::: "memory");
    bulk_ld_e<192>(sb + OFF_BIAS, bias, sb + BAR_BIAS);
    tma_stage_e(sb + OFF_IN, &tmx0, sb + BAR_INF, 0, tile_x >> 1, tile_y - 1);
    asm volatile("prefetch.tensormap [%0];" ::"l"(&tmx) : "memory");
  }
  TR(2);

  uint32_t AD[4];
  {
    const uint32_t lin0 = sb + OFF_IN + (((lane >> 3) & 1) ? PLANE : 0) + wi * 2 * ROWP + (lane & 7) * 64 + (lane >> 4) * 16;
#pragma unroll
    for (int n = 0; n < 4; n++) {
      uint32_t l = lin0 + 64 * n;
      AD[n] = l ^ ((l >> 3) & 0x30u);
      asm volatile("" : "+r"(AD[n]));
    }
  }
  Ctx cx;
  cx.sb = sb;
  cx.dres = ((uint64_t)(1024 >> 4) << 16) | ((uint64_t)(512 >> 4) << 32) | ((uint64_t)2 << 62) | (uint64_t)((sb & 0x3FFFF) >> 4);
  cx.wg = wg;

  float acc[4][48];
  const uint32_t baddr = sb + OFF_BIAS + (lane & 3) * 16;
  if (wg == 1) {
    if (wi != 1) {
      TRA(80);
      const uint8_t* cp = wprep + OFF_SYNC + (lane & 3) * 128;
      uint32_t v, n = 0;
      do {
        asm volatile("ld.acquire.gpu.global.u32 %0, [%1];" : "=r"(v) : "l"(cp) : "memory");
        if (++n > 4000000u) __trap();
      } while (!__all_sync(0xffffffffu, v == 27));
    }
    if (wi == 0) {
      asm volatile("fence.proxy.async.global;" ::: "memory");
      TRA(81);
#pragma unroll
      for (int c = 0; c < 6; c++) {
        bulk_ld_e<3 * GRP>(sb + c * 3 * GRP, wprep + c * 3 * GRP, sb + BAR_RES + c * 8);
        if (c < 3) bulk_ld_e<GRP>(sb + OFF_RING + c * GRP, wprep + OFF_RING + c * GRP, sb + BAR_WF + c * 8);
        if (c == S1POS) tma_stage_e(sb + OFF_IN + STAGE, &tmx, sb + BAR_INF + 8, 32, tile_x >> 1, tile_y - 1);
        if (c == S2POS) tma_stage_e(sb + OFF_IN + 2 * STAGE, &tmx, sb + BAR_INF + 16, 64, tile_x >> 1, tile_y - 1);
      }
      TRA(82);
    } else if (wi >= 2) {
      pf_unit(tile_x, tile_y, wi - 2, 2, 5);
    }
    asm volatile("bar.sync 2, 128;" ::: "memory");
    if (wi == 1) {
      uint32_t old = 0;
      if (lane == 0) asm volatile("atom.relaxed.gpu.global.inc.u32 %0, [%1], 127;" : "=r"(old) : "l"(wprep + OFF_SYNC + 512) : "memory");
      if (__shfl_sync(0xffffffffu, old, 0) == 127 && lane < 4) asm volatile("st.relaxed.gpu.global.u32 [%0], 0;" ::"l"(wprep + OFF_SYNC + lane * 128) : "memory");
      __syncwarp();
    }
  } else {
    asm volatile("bar.sync 1, 160;" ::: "memory");
  }
  mbar_wait(sb + BAR_BIAS, 0);
#pragma unroll
  for (int m = 0; m < 3; m++) {
    uint32_t bb[4];
    lds128(baddr + m * 64, bb);
#pragma unroll
    for (int jj = 0; jj < 4; jj++)
#pragma unroll
      for (int h = 0; h < 2; h++) {
        const int i0 = 4 * (4 * m + jj) + 2 * h;
        acc[1][i0] = vlo(bb[jj]); acc[1][i0 + 1] = vhi(bb[jj]);
        acc[0][i0] = acc[0][i0 + 1] = acc[2][i0] = acc[2][i0 + 1] = acc[3][i0] = acc[3][i0 + 1] = 0.f;
      }
  }
  if (wg == 0) {
    mbar_wait(sb + BAR_INF, 0);
    TR(3);
    mbar_wait(sb + BAR_RES, 0);
  }

  for (int u = -wg;; u += 2) {
    const bool st = u >= 0;
    uint8_t* op = nullptr;
    uint32_t bb[4];
    if (st) {
      cx.first = (u == 0);
      TR(4 + 4 * (u >> 1));
      uint32_t D0[8], D1[8], D2[8];
      ldraw<0, 0, 0>(AD, D0); ldraw<0, 2, 0>(AD, D2); ldraw<0, 0, 1>(AD, D0); ldraw<0, 2, 1>(AD, D2); ldraw<0, 1, 0>(AD, D1);
      bulk_ld_p<GRP>(wi, cx.first ? 8 : 0, sb + OFF_RING + GRP, wprep + OFF_RING + GRP, sb + BAR_WF + 8);
      sfence();
      chunk<0>(cx, acc, D0, D1, D2, AD);
      TC(1); chunk<1>(cx, acc, D0, D1, D2, AD);
      TC(2); chunk<2>(cx, acc, D0, D1, D2, AD);
      TC(3); chunk<3>(cx, acc, D0, D1, D2, AD);
      TC(4); chunk<4>(cx, acc, D0, D1, D2, AD);
      TC(5); chunk<5>(cx, acc, D0, D1, D2, AD);
      TR(5 + 4 * (u >> 1));
      const int uq = (u * 11) >> 5, ur = u - 3 * uq;
      op = reinterpret_cast<uint8_t*>(out) +
           (uint32_t)(((tile_y + uq * 8 + wi * 2) * IMG + tile_x + ur * 16 + 2 * (lane >> 2)) * (CH * 2) + (lane & 3) * 16);
      wg_wait<3>();
#pragma unroll
      for (int i = 0; i < 3; i++)
#pragma unroll
        for (int j = 0; j < 48; j++) asm volatile("" : "+f"(acc[i][j])::"memory");
      piece<0, 0, 0, true>(acc, bb, op, true);
      wg_wait<0>();
#pragma unroll
      for (int j = 0; j < 48; j++) asm volatile("" : "+f"(acc[3][j])::"memory");
      mbar_arrive1(sb + BAR_WE + 40);
    }
    if (u == 8) {
      piece<1, 0, 0, false>(acc, bb, op, true); piece<2, 0, 0, false>(acc, bb, op, true);
      piece<0, 1, 0, false>(acc, bb, op, true); piece<1, 1, 0, false>(acc, bb, op, true); piece<2, 1, 0, false>(acc, bb, op, true);
      piece<0, 0, 1, false>(acc, bb, op, true); piece<1, 0, 1, false>(acc, bb, op, true); piece<2, 0, 1, false>(acc, bb, op, true);
      piece<0, 1, 1, false>(acc, bb, op, true); piece<1, 1, 1, false>(acc, bb, op, true); piece<2, 1, 1, false>(acc, bb, op, true);
      break;
    }
    const int un = u + 2;
    const bool more = un <= 8;
    const uint32_t po = wg ^ 1;
    auto refill_w = [&](int slot, int c) { bulk_ld_e<GRP>(sb + OFF_RING + slot * GRP, wprep + OFF_RING + c * GRP, sb + BAR_WF + slot * 8); };
    auto refill_in = [&](int p, int v) {
      const int q = (v * 11) >> 5, r = v - 3 * q;
      tma_stage_e(sb + OFF_IN + p * STAGE, &tmx, sb + BAR_INF + p * 8, p * 32, (tile_x + r * 16) >> 1, tile_y + q * 8 - 1);
    };
    lds128(baddr, bb);
    if (st && wi < 2) {
      mbar_wait(sb + BAR_WE + 40, wg);
      if (wi == 0) refill_w(2, 2); else refill_in(2, u + 1);
    }
    sfence();
    piece<0, 0, 1, true>(acc, bb, op, st); piece<0, 1, 0, true>(acc, bb, op, st);
    if (wi == 2) { mbar_wait(sb + BAR_WE, po); refill_w(0, 3); }
    if (wi == 3) { mbar_wait(sb + BAR_INE, po); if (more) refill_in(0, un); }
    piece<0, 1, 1, true>(acc, bb, op, st);
    lds128(baddr + 64, bb);
    piece<1, 0, 0, true>(acc, bb, op, st);
    if (wi == 0) { mbar_wait(sb + BAR_WE + 8, po); refill_w(1, 4); }
    piece<1, 0, 1, true>(acc, bb, op, st); piece<1, 1, 0, true>(acc, bb, op, st);
    if (wi == 1) { mbar_wait(sb + BAR_WE + 16, po); refill_w(2, 5); }
    piece<1, 1, 1, true>(acc, bb, op, st);
    if (wi == 2 && more) { mbar_wait(sb + BAR_INE + 8, po); refill_in(1, un); }
    lds128(baddr + 128, bb);
    piece<2, 0, 0, true>(acc, bb, op, st); piece<2, 0, 1, true>(acc, bb, op, st);
    if (wi == 3 && more) { mbar_wait(sb + BAR_WE + 24, po); refill_w(0, 0); }
    piece<2, 1, 0, true>(acc, bb, op, st); piece<2, 1, 1, true>(acc, bb, op, st);
    TR(6 + 4 * ((u + 1) >> 1));
    if (!more) break;
    if (!st) {
#pragma unroll
      for (int c = 0; c < 6; c++) mbar_wait(sb + BAR_RES + c * 8, 0);
    }
    mbar_wait(sb + BAR_INF, wg);
    mbar_wait(sb + BAR_WE + 32, po);
  }
  TR(70); TRG(71);
}

typedef CUresult (*EncodeFn)(CUtensorMap*, CUtensorMapDataType, cuuint32_t, void*, const cuuint64_t*, const cuuint64_t*, const cuuint32_t*,
                             const cuuint32_t*, CUtensorMapInterleave, CUtensorMapSwizzle, CUtensorMapL2promotion, CUtensorMapFloatOOBfill);

}

extern "C" void kernel_launch(void* const* d_in, const int* in_sizes, int n_in, void* d_out, int out_size) {
  const __nv_bfloat16* x = (const __nv_bfloat16*)d_in[0];
  const __nv_bfloat16* w = (const __nv_bfloat16*)d_in[1];
  const __nv_bfloat16* b = (const __nv_bfloat16*)d_in[2];
  __nv_bfloat16* out = (__nv_bfloat16*)d_out;

  static EncodeFn enc = nullptr;
  static void* wp = nullptr;
  if (!enc) {
    cudaGetSymbolAddress(&wp, g_wprep);
    cudaDriverEntryPointQueryResult qr;
    cudaGetDriverEntryPoint("cuTensorMapEncodeTiled", (void**)&enc, cudaEnableDefault, &qr);
    cudaFuncSetAttribute(conv_kernel, cudaFuncAttributeMaxDynamicSharedMemorySize, SMEM_BYTES);
  }
  CUtensorMap tmx;
  cuuint64_t dims[4] = {(cuuint64_t)CH, (cuuint64_t)(IMG / 2), 2, (cuuint64_t)IMG};
  cuuint64_t strides[3] = {(cuuint64_t)CH * 4, (cuuint64_t)CH * 2, (cuuint64_t)IMG * CH * 2};
  cuuint32_t box[4] = {32, 9, 1, 10};
  cuuint32_t es[4] = {1, 1, 1, 1};
  enc(&tmx, CU_TENSOR_MAP_DATA_TYPE_BFLOAT16, 4, (void*)x, dims, strides, box, es, CU_TENSOR_MAP_INTERLEAVE_NONE,
      CU_TENSOR_MAP_SWIZZLE_64B, CU_TENSOR_MAP_L2_PROMOTION_L2_128B, CU_TENSOR_MAP_FLOAT_OOB_FILL_NONE);

  CUtensorMap tmx0;
  enc(&tmx0, CU_TENSOR_MAP_DATA_TYPE_BFLOAT16, 4, (void*)x, dims, strides, box, es, CU_TENSOR_MAP_INTERLEAVE_NONE,
      CU_TENSOR_MAP_SWIZZLE_64B, CU_TENSOR_MAP_L2_PROMOTION_L2_64B, CU_TENSOR_MAP_FLOAT_OOB_FILL_NONE);
  conv_kernel<<<128, 256, SMEM_BYTES>>>(tmx, tmx0, (uint8_t*)wp, (const uint8_t*)x, w, b, out);
}
```

```cpp
#include <cuda_runtime.h>
#include <cuda.h>
#include <cuda_bf16.h>
#include <stdint.h>

namespace {

constexpr int IMG = 384, CH = 96;
constexpr int NCTA = 132, NPREP = 36;
constexpr int NL = 3;
constexpr uint32_t TS1 = 1300, TS2 = 3000, TSP = 3800;
constexpr int LEAD0 = 4;
constexpr int PM0 = 0x0a, PM1 = 0x24;
constexpr uint32_t BLK = 3072;
constexpr uint32_t GRP = 3 * BLK;
constexpr uint32_t CHK = 4 * GRP;
constexpr uint32_t PLANE = 5760;
constexpr uint32_t STAGE = 2 * PLANE;
constexpr uint32_t ROWP = 576;
constexpr uint32_t OFF_IN = 5 * CHK;
constexpr uint32_t OFF_BAR = OFF_IN + 3 * STAGE;
constexpr uint32_t IN0_WG1 = 3 * STAGE + 256;
constexpr uint32_t BAR_INF = OFF_BAR;
constexpr uint32_t BAR_WF = OFF_BAR + 32;
constexpr uint32_t BAR_RES = OFF_BAR + 40;
constexpr uint32_t BAR_INE = OFF_BAR + 80;
constexpr uint32_t BAR_WE = OFF_BAR + 96;
constexpr uint32_t BAR_GO = OFF_BAR + 104;
constexpr uint32_t BAR_RAW = OFF_BAR + 160;
constexpr uint32_t OFF_BIAS = OFF_IN + IN0_WG1 + STAGE;
constexpr uint32_t SMEM_BYTES = OFF_BIAS + 1536;

constexpr uint32_t OFF_SYNC = 6 * CHK;
__device__ __align__(1024) uint8_t g_wprep[OFF_SYNC + 1024];

__device__ __forceinline__ void wg_fence() { asm volatile("wgmma.fence.sync.aligned;" ::: "memory"); }
__device__ __forceinline__ void wg_commit() { asm volatile("wgmma.commit_group.sync.aligned;" ::: "memory"); }
template <int N> __device__ __forceinline__ void wg_wait() { asm volatile("wgmma.wait_group.sync.aligned %0;" ::"n"(N) : "memory"); }
__device__ __forceinline__ void sfence() { asm volatile("pmevent 0;" ::: "memory"); }

__device__ __forceinline__ void wgmma96(float (&d)[48], uint32_t a0, uint32_t a1, uint32_t a2, uint32_t a3, uint64_t db, int sc) {
  asm volatile(
      "{\n.reg .pred p;\nsetp.ne.b32 p, %53, 0;\n"
      "wgmma.mma_async.sync.aligned.m64n96k16.f32.bf16.bf16 "
      "{%0,%1,%2,%3,%4,%5,%6,%7,%8,%9,%10,%11,%12,%13,%14,%15,%16,%17,%18,%19,%20,%21,%22,%23,"
      "%24,%25,%26,%27,%28,%29,%30,%31,%32,%33,%34,%35,%36,%37,%38,%39,%40,%41,%42,%43,%44,%45,%46,%47},"
      "{%48,%49,%50,%51}, %52, p, 1, 1, 1;\n}\n"
      : "+f"(d[0]), "+f"(d[1]), "+f"(d[2]), "+f"(d[3]), "+f"(d[4]), "+f"(d[5]), "+f"(d[6]), "+f"(d[7]), "+f"(d[8]), "+f"(d[9]),
        "+f"(d[10]), "+f"(d[11]), "+f"(d[12]), "+f"(d[13]), "+f"(d[14]), "+f"(d[15]), "+f"(d[16]), "+f"(d[17]), "+f"(d[18]),
        "+f"(d[19]), "+f"(d[20]), "+f"(d[21]), "+f"(d[22]), "+f"(d[23]), "+f"(d[24]), "+f"(d[25]), "+f"(d[26]), "+f"(d[27]),
        "+f"(d[28]), "+f"(d[29]), "+f"(d[30]), "+f"(d[31]), "+f"(d[32]), "+f"(d[33]), "+f"(d[34]), "+f"(d[35]), "+f"(d[36]),
        "+f"(d[37]), "+f"(d[38]), "+f"(d[39]), "+f"(d[40]), "+f"(d[41]), "+f"(d[42]), "+f"(d[43]), "+f"(d[44]), "+f"(d[45]),
        "+f"(d[46]), "+f"(d[47])
      : "r"(a0), "r"(a1), "r"(a2), "r"(a3), "l"(db), "r"(sc));
}

__device__ __forceinline__ void acc_fence(float (&d)[48]) {
#pragma unroll
  for (int j = 0; j < 48; j++) asm volatile("" : "+f"(d[j])::"memory");
}
__device__ __forceinline__ void ldsm4(uint32_t addr, uint32_t* r) {
  asm volatile("ldmatrix.sync.aligned.m8n8.x4.shared.b16 {%0,%1,%2,%3}, [%4];"
               : "=r"(r[0]), "=r"(r[1]), "=r"(r[2]), "=r"(r[3]) : "r"(addr) : "memory");
}
__device__ __forceinline__ void stsm4(uint32_t addr, const uint32_t (&r)[4]) {
  asm volatile("stmatrix.sync.aligned.m8n8.x4.shared.b16 [%0], {%1,%2,%3,%4};" ::"r"(addr), "r"(r[0]), "r"(r[1]), "r"(r[2]), "r"(r[3]) : "memory");
}
__device__ __forceinline__ void lds128(uint32_t addr, uint32_t (&r)[4]) {
  asm volatile("ld.shared.v4.u32 {%0,%1,%2,%3}, [%4];" : "=r"(r[0]), "=r"(r[1]), "=r"(r[2]), "=r"(r[3]) : "r"(addr) : "memory");
}
template <uint32_t K> __device__ __forceinline__ uint32_t vxor(uint32_t a) {
  uint32_t r;
  asm volatile("xor.b32 %0, %1, %2;" : "=r"(r) : "r"(a), "n"(K));
  return r;
}
__device__ __forceinline__ float fhp(float a, float h) {
  float r;
  asm volatile("fma.rn.f32 %0, %2, 0f3F000000, %1;" : "=f"(r) : "f"(a), "f"(h));
  return r;
}
__device__ __forceinline__ float fhm(float a, float h) {
  float r;
  asm volatile("fma.rn.f32 %0, %2, 0fBF000000, %1;" : "=f"(r) : "f"(a), "f"(h));
  return r;
}
template <int H> __device__ __forceinline__ float vlo(uint32_t v) {
  uint32_t r;
  if (H == 0) asm volatile("shl.b32 %0, %1, 16;" : "=r"(r) : "r"(v));
  else asm volatile("prmt.b32 %0, %1, 0, 0x1044;" : "=r"(r) : "r"(v));
  return __uint_as_float(r);
}
template <int H> __device__ __forceinline__ float vhi(uint32_t v) {
  uint32_t r;
  if (H == 0) asm volatile("and.b32 %0, %1, 0xffff0000;" : "=r"(r) : "r"(v));
  else asm volatile("prmt.b32 %0, %1, 0, 0x3244;" : "=r"(r) : "r"(v));
  return __uint_as_float(r);
}
template <bool SUB> __device__ __forceinline__ uint32_t bop(uint32_t a, uint32_t b) {
  uint32_t r;
  if (SUB) asm volatile("sub.rn.bf16x2 %0, %1, %2;" : "=r"(r) : "r"(a), "r"(b));
  else asm volatile("add.rn.bf16x2 %0, %1, %2;" : "=r"(r) : "r"(a), "r"(b));
  return r;
}
__device__ __forceinline__ uint32_t pack2(float lo, float hi) {
  uint32_t r;
  asm volatile("cvt.rn.bf16x2.f32 %0, %1, %2;" : "=r"(r) : "f"(hi), "f"(lo));
  return r;
}
__device__ __forceinline__ void mbar_init(uint32_t bar, uint32_t cnt) {
  asm volatile("mbarrier.init.shared::cta.b64 [%0], %1;" ::"r"(bar), "r"(cnt) : "memory");
}
__device__ __forceinline__ void mbar_wait(uint32_t bar, uint32_t parity) {
  asm volatile(
      "{\n.reg .pred p, q;\n.reg .u32 n;\n"
      "mov.u32 n, 0;\n"
      "LAB_WAIT:\n"
      "mbarrier.try_wait.parity.shared::cta.b64 p, [%0], %1;\n"
      "@p bra LAB_DONE;\n"
      "add.u32 n, n, 1;\n"
      "setp.lt.u32 q, n, 400000;\n"
      "@q bra LAB_WAIT;\n"
      "trap;\n"
      "LAB_DONE:\n}\n" ::"r"(bar), "r"(parity) : "memory");
}
__device__ __forceinline__ bool mbar_test0(uint32_t bar) {
  uint32_t r;
  asm volatile("{\n.reg .pred p;\nmbarrier.test_wait.parity.shared::cta.b64 p, [%1], 0;\nselp.u32 %0, 1, 0, p;\n}\n" : "=r"(r) : "r"(bar) : "memory");
  return r;
}
__device__ __forceinline__ void mbar_arrive1(uint32_t bar) {
  asm volatile("{\n.reg .pred e;\nelect.sync _|e, 0xffffffff;\n@e mbarrier.arrive.shared::cta.b64 _, [%0];\n}\n" ::"r"(bar) : "memory");
}
__device__ __forceinline__ bool elect_one() {
  uint32_t r;
  asm volatile("{\n.reg .pred p;\nelect.sync _|p, 0xffffffff;\nselp.u32 %0, 1, 0, p;\n}\n" : "=r"(r));
  return r;
}
__device__ __forceinline__ void tma_stage(uint32_t dst, const CUtensorMap* tm, uint32_t bar, int c, int xh, int y) {
  asm volatile("{\n.reg .pred p;\nelect.sync _|p, 0xffffffff;\n"
               "@p mbarrier.arrive.expect_tx.shared::cta.b64 _, [%3], %8;\n"
               "@p cp.async.bulk.tensor.4d.shared::cluster.global.mbarrier::complete_tx::bytes [%0], [%2, {%4, %5, 1, %7}], [%3];\n"
               "@p cp.async.bulk.tensor.4d.shared::cluster.global.mbarrier::complete_tx::bytes [%1], [%2, {%4, %6, 0, %7}], [%3];\n}\n"
               ::"r"(dst), "r"(dst + PLANE), "l"(tm), "r"(bar), "r"(c), "r"(xh - 1), "r"(xh), "r"(y), "n"(STAGE) : "memory");
  __syncwarp();
}
__device__ __forceinline__ void bulk_chunk(uint32_t dst, const void* src, uint32_t bar) {
  asm volatile("{\n.reg .pred p;\nelect.sync _|p, 0xffffffff;\n"
               "@p mbarrier.arrive.expect_tx.shared::cta.b64 _, [%2], %3;\n"
               "@p cp.async.bulk.shared::cluster.global.mbarrier::complete_tx::bytes [%0], [%1], %3, [%2];\n}\n"
               ::"r"(dst), "l"(src), "r"(bar), "n"(CHK) : "memory");
  __syncwarp();
}

__device__ __forceinline__ void wino_w(uint32_t a, uint32_t b, uint32_t c, uint32_t& u1, uint32_t& u2) {
  const float s0 = __uint_as_float(a << 16) + __uint_as_float(c << 16), s1 = __uint_as_float(a & 0xffff0000u) + __uint_as_float(c & 0xffff0000u);
  const float b0 = __uint_as_float(b << 16), b1 = __uint_as_float(b & 0xffff0000u);
  u1 = pack2(s0 + b0, s1 + b1);
  u2 = pack2(s0 - b0, s1 - b1);
}
__device__ __forceinline__ void prep_local(uint32_t base, int lane) {
  uint32_t g[3][3][4];
  const uint32_t ra = base + (lane >> 2) * 192 + (lane & 3) * 16;
#pragma unroll
  for (int m = 0; m < 3; m++)
#pragma unroll
    for (int dy = 0; dy < 3; dy++) lds128(ra + dy * GRP + m * 64, g[dy][m]);
  const uint32_t wo = (lane & 7) * 64 + (((lane >> 3) ^ ((lane & 7) >> 1)) * 16);
#pragma unroll
  for (int m = 0; m < 3; m++) {
    uint32_t u1[4], u2[4];
#pragma unroll
    for (int j = 0; j < 4; j++) wino_w(g[0][m][j], g[1][m][j], g[2][m][j], u1[j], u2[j]);
    stsm4(base + wo + m * 512, g[0][m]);
    stsm4(base + wo + m * 512 + GRP, u1);
    stsm4(base + wo + m * 512 + 2 * GRP, u2);
    stsm4(base + wo + m * 512 + 3 * GRP, g[2][m]);
  }
}
__device__ __forceinline__ void prep_load(const __nv_bfloat16* __restrict__ w, int item, int lane, uint32_t (&g)[3][4], bool on) {
  const int t = (item * 171) >> 9, kh = (item * 57) >> 9, m = item - 3 * t, dx = t - 3 * kh;
  const uint8_t* p = reinterpret_cast<const uint8_t*>(w) + (uint32_t)((dx * 96 + kh * 8) * 192 + m * 64 + (lane >> 2) * 192 + (lane & 3) * 4);
#pragma unroll
  for (int dy = 0; dy < 3; dy++)
#pragma unroll
    for (int q = 0; q < 4; q++)
      asm volatile("{\n.reg .pred p;\nsetp.ne.u32 p, %2, 0;\n@p ld.global.nc.u32 %0, [%1];\n}\n" : "=r"(g[dy][q]) : "l"(p + dy * 55296 + q * 16), "r"((uint32_t)on));
}
__device__ __forceinline__ void prep_store(uint8_t* wprep, int item, int lane, const uint32_t (&g)[3][4]) {
  const int t = (item * 171) >> 9, kh = (item * 57) >> 9, m = item - 3 * t, dx = t - 3 * kh, k = lane >> 2, jj = lane & 3;
  uint32_t u1[4], u2[4];
#pragma unroll
  for (int q = 0; q < 4; q++) wino_w(g[0][q], g[1][q], g[2][q], u1[q], u2[q]);
  uint8_t* res = wprep + (uint32_t)((kh >> 1) * CHK + dx * BLK + (kh & 1) * 1536 + m * 512 + k * 64 + ((jj ^ (k >> 1)) * 16));
  *reinterpret_cast<uint4*>(res) = make_uint4(g[0][0], g[0][1], g[0][2], g[0][3]);
  *reinterpret_cast<uint4*>(res + GRP) = make_uint4(u1[0], u1[1], u1[2], u1[3]);
  *reinterpret_cast<uint4*>(res + 2 * GRP) = make_uint4(u2[0], u2[1], u2[2], u2[3]);
  *reinterpret_cast<uint4*>(res + 3 * GRP) = make_uint4(g[2][0], g[2][1], g[2][2], g[2][3]);
}

template <bool SUB, int SC, class H0, class H1, class H2, class H3>
__device__ __forceinline__ void step(float (&acc)[48], const uint32_t* a, const uint32_t* b, uint64_t db, bool odd, H0 h0, H1 h1, H2 h2, H3 h3) {
  uint32_t p[4], q[4];
  wg_wait<3>();
  h0();
#pragma unroll
  for (int i = 0; i < 4; i++) p[i] = bop<SUB>(a[i], b[i]);
  wg_fence();
  wgmma96(acc, p[0], p[1], p[2], p[3], db, SC);
  wg_commit();
  h1();
  sfence();
  wg_wait<3>();
#pragma unroll
  for (int i = 0; i < 4; i++) q[i] = bop<SUB>(a[4 + i], b[4 + i]);
  wg_fence();
  wgmma96(acc, q[0], q[1], q[2], q[3], db + ((2 * BLK) >> 4), 1);
  wg_commit();
  h2();
  wg_wait<3>();
  const uint32_t r0 = odd ? q[1] : p[1], r1 = odd ? p[0] : q[0], r2 = odd ? q[3] : p[3], r3 = odd ? p[2] : q[2];
  wg_fence();
  wgmma96(acc, r0, r1, r2, r3, db + (BLK >> 4), 1);
  wg_commit();
  h3();
  sfence();
}

struct Ctx {
  uint32_t sb;
  uint32_t d0, dres;
  uint32_t dstep;
  int wg;
  bool first, odd;
};

template <int CK, int R, int J>
__device__ __forceinline__ void ldraw(const uint32_t (&AD)[5], uint32_t* dst) {
  constexpr int N = R + J;
  constexpr bool X = (((CK & 1) ^ (CK >> 1) ^ (N >> 2)) & 1) != 0;
  constexpr uint32_t OFF = (CK >> 1) * STAGE + R * 512 + (N >> 2) * 256;
  constexpr uint32_t K = (uint32_t)(1 + 2 * CK + J) << 18;
  if (CK < 6) ldsm4(vxor<K | (X ? 32u : 0u)>(AD[N & 3]) + (CK < 2 ? AD[4] : 0u) + (OFF - K), dst + 4 * J);
}

template <int CK>
__device__ __forceinline__ void chunk(const Ctx& cx, float (&acc)[4][48], uint32_t (&D0)[8], uint32_t (&D1)[8], uint32_t (&D2)[8],
                                      const uint32_t (&AD)[5]) {
  constexpr int P = CK >> 1;
  constexpr int SC = CK != 0;
  const uint32_t sb = cx.sb;
  constexpr uint64_t DHI = 0x8000006000000000ull;
  const uint64_t db = DHI | ((CK == 0 || CK == 5) ? cx.d0 : cx.dres + cx.dstep * CK);
  auto nop = []() {};
  uint32_t D3[8];
  constexpr bool EARLY = CK == 1 || CK == 3, LATE = CK == 4;
  constexpr uint32_t BT = EARLY ? BAR_INF + (P + 1) * 8 : BAR_WF;
  bool t = false;
  uint32_t slow = 0;
  auto test = [&]() { t = mbar_test0(sb + BT); };
  auto combine = [&]() {
    asm volatile("{\n.reg .pred a, g;\nsetp.ne.u32 a, %1, 0;\nsetp.eq.u32 g, %2, 0;\nxor.pred a, a, g;\nselp.u32 %0, 1, 0, a;\n}\n"
                 : "=r"(slow) : "r"((uint32_t)t), "r"(cx.wg));
  };
  step<true, SC>(acc[0], D0, D2, db, cx.odd, nop,
                 [&]() {
                   if (CK == 0) ldraw<0, 1, 0>(AD, D1);
                   ldraw<CK, 1, 1>(AD, D1);
                   if (EARLY) test();
                 },
                 [&]() { if (EARLY) combine(); }, [&]() { ldraw<CK, 3, 0>(AD, D3); });
  if (EARLY && __builtin_expect(slow, 0)) mbar_wait(sb + BT, cx.wg);
  step<false, 1>(acc[1], D1, D2, db + (GRP >> 4), cx.odd,
                 [&]() {
                   if (CK == 1) mbar_arrive1(sb + BAR_WE);
                   if (CK == 5) mbar_arrive1(sb + BAR_GO);
                 },
                 [&]() { ldraw<CK, 3, 1>(AD, D3); }, [&]() { if (EARLY) mbar_arrive1(sb + BAR_INE + P * 8); },
                 [&]() { ldraw<CK + 1, 0, 0>(AD, D0); });
  step<true, SC>(acc[2], D2, D1, db + ((2 * GRP) >> 4), cx.odd, nop,
                 [&]() {
                   ldraw<CK + 1, 2, 0>(AD, D2);
                   if (LATE) test();
                 },
                 [&]() { if (LATE) combine(); }, [&]() { ldraw<CK + 1, 2, 1>(AD, D2); });
  if (LATE && __builtin_expect(slow, 0)) mbar_wait(sb + BT, cx.wg);
  step<true, SC>(acc[3], D3, D1, db + ((3 * GRP) >> 4), cx.odd, nop, [&]() { ldraw<CK + 1, 0, 1>(AD, D0); }, nop,
                 [&]() { ldraw<CK + 1, 1, 0>(AD, D1); });
  if (CK < 4 && __builtin_expect(cx.first, 0)) mbar_wait(sb + BAR_RES + (CK + 1) * 8, 0);
}

template <int M, int H, int ROW, bool PACE>
__device__ __forceinline__ void piece(float (&acc)[4][48], const uint32_t (&bb)[4], uint8_t* const (&op)[2]) {
  uint32_t y[4];
  auto pf = [](int mask, int i) { if (PACE && ((mask >> i) & 1)) sfence(); };
#pragma unroll
  for (int jj = 0; jj < 4; jj++) {
    const int i0 = 4 * (4 * M + jj) + 2 * H;
    float v0, v1;
    if (ROW == 0) {
      v0 = fhp(acc[0][i0], acc[1][i0]); pf(PM0, 0);
      v1 = fhp(acc[0][i0 + 1], acc[1][i0 + 1]); pf(PM0, 1);
      v0 = fhp(v0, acc[2][i0]); pf(PM0, 2);
      v1 = fhp(v1, acc[2][i0 + 1]); pf(PM0, 3);
      y[jj] = pack2(v0, v1); pf(PM0, 4);
    } else {
      v0 = fhp(acc[3][i0], acc[1][i0]); pf(PM1, 0);
      if (PACE) acc[1][i0] = vlo<H>(bb[jj]);
      pf(PM1, 1);
      v0 = fhm(v0, acc[2][i0]); pf(PM1, 2);
      v1 = fhp(acc[3][i0 + 1], acc[1][i0 + 1]); pf(PM1, 3);
      if (PACE) acc[1][i0 + 1] = vhi<H>(bb[jj]);
      pf(PM1, 4);
      v1 = fhm(v1, acc[2][i0 + 1]); pf(PM1, 5);
      y[jj] = pack2(v0, v1); pf(PM1, 6);
    }
  }
  asm volatile("st.global.L1::no_allocate.v4.u32 [%0], {%1,%2,%3,%4};" ::"l"(op[H] + ROW * IMG * CH * 2 + M * 64), "r"(y[0]), "r"(y[1]), "r"(y[2]),
               "r"(y[3]) : "memory");
  if (!PACE) sfence();
}

__global__ void __launch_bounds__(256, 1)
conv_kernel(uint8_t* wprep, const __nv_bfloat16* __restrict__ w, const __nv_bfloat16* __restrict__ bias, __nv_bfloat16* __restrict__ out,
            const __grid_constant__ CUtensorMap tmw, const __grid_constant__ CUtensorMap tmx64, const __grid_constant__ CUtensorMap tmx128,
            const __grid_constant__ CUtensorMap tmx256) {
  extern __shared__ __align__(1024) uint8_t smem[];
  const uint32_t sb = (uint32_t)__cvta_generic_to_shared(smem);
  uint32_t tstart;
  asm volatile("mov.u32 %0, %%clock;" : "=r"(tstart));
  const int tid = threadIdx.x;
  const int warp = __shfl_sync(0xffffffffu, tid >> 5, 0);
  const int wg = warp >> 2, wi = warp & 3, lane = tid & 31;
  const bool prepper = blockIdx.x < NPREP;
  const int ubase = prepper ? 8 * blockIdx.x : 9 * blockIdx.x - NPREP;
  const int ulast = prepper ? 7 : 8;
  const int nl = prepper ? 0 : NL;
  auto unit_xy = [&](int v, int& x0, int& y0) {
    const int id = ubase + v, st = (id * 911) >> 17, rem = id - 144 * st, q = (rem * 171) >> 9;
    x0 = st * 48 + (rem - 3 * q) * 16;
    y0 = q * 8;
  };
  auto spin_until = [&](uint32_t t) {
    uint32_t c;
    do { asm volatile("mov.u32 %0, %%clock;" : "=r"(c)); } while (c - tstart < t);
  };
  auto load_in = [&](int p, int v, const CUtensorMap* tm) {
    int x0, y0;
    unit_xy(v, x0, y0);
    const bool alt = p == 0 && (v & 1);
    tma_stage(sb + OFF_IN + (alt ? IN0_WG1 : p * STAGE), tm, sb + BAR_INF + (alt ? 3 : p) * 8, ((v & 1) ? 2 - p : p) * 32, x0 >> 1, y0 - 1);
  };
  auto refill_w = [&](int par) { bulk_chunk(sb, wprep + (par ? 0 : 5 * CHK), sb + BAR_WF); };

  uint32_t gpre[3][4], b0[3][4];
  prep_load(w, min(blockIdx.x * 3 + warp, 107), lane, gpre, prepper && warp < 3);
#pragma unroll
  for (int m = 0; m < 3; m++)
    asm volatile("ld.global.nc.v4.u32 {%0,%1,%2,%3}, [%4];" : "=r"(b0[m][0]), "=r"(b0[m][1]), "=r"(b0[m][2]), "=r"(b0[m][3])
                 : "l"(reinterpret_cast<const uint8_t*>(bias) + (uint32_t)((lane & 3) * 16 + m * 64)));
  uint32_t ready = 0;
  if (warp == 4) {
    if (elect_one()) {
#pragma unroll
      for (int c = 0; c < NL; c++) mbar_init(sb + BAR_RAW + c * 8, 1);
      mbar_init(sb + BAR_INF, 1);
      asm volatile("fence.mbarrier_init.release.cluster;" ::: "memory");
      if (!prepper) {
        int x0, y0;
        unit_xy(0, x0, y0);
#pragma unroll
        for (int c = 0; c < NL; c++) {
          if (c == NL - 1)
            asm volatile("mbarrier.arrive.expect_tx.shared::cta.b64 _, [%3], %7;\n"
                         "cp.async.bulk.tensor.4d.shared::cluster.global.mbarrier::complete_tx::bytes [%0], [%2, {0, %4, 1, %6}], [%3];\n"
                         "cp.async.bulk.tensor.4d.shared::cluster.global.mbarrier::complete_tx::bytes [%1], [%2, {0, %5, 0, %6}], [%3];\n"
                         ::"r"(sb + OFF_IN), "r"(sb + OFF_IN + PLANE), "l"(&tmx64), "r"(sb + BAR_INF), "r"((x0 >> 1) - 1), "r"(x0 >> 1),
                           "r"(y0 - 1), "n"(STAGE) : "memory");
          asm volatile("mbarrier.arrive.expect_tx.shared::cta.b64 _, [%2], %4;\n"
                       "cp.async.bulk.tensor.3d.shared::cluster.global.mbarrier::complete_tx::bytes [%0], [%1, {0, %3, 0}], [%2];\n"
                       ::"r"(sb + c * CHK), "l"(&tmw), "r"(sb + BAR_RAW + c * 8), "r"(2 * c), "n"(3 * GRP) : "memory");
        }
      }
#pragma unroll
      for (int i = 1; i < 14; i++) mbar_init(sb + OFF_BAR + i * 8, (i >= 5 && i < 5 + NL) ? (prepper ? 1 : 6) : i < 10 ? 1 : 4);
      asm volatile("fence.mbarrier_init.release.cluster;" ::: "memory");
    }
    __syncwarp();
    asm volatile("bar.arrive 1, 256;" ::: "memory");
    asm volatile("ld.relaxed.gpu.global.u32 %0, [%1];" : "=r"(ready) : "l"(wprep + OFF_SYNC + (lane & 3) * 128) : "memory");
  }
  if (warp != 4) asm volatile("bar.sync 1, 256;" ::: "memory");
  if (prepper) {
    if (warp < 3) {
      prep_store(wprep, blockIdx.x * 3 + warp, lane, gpre);
      asm volatile("fence.proxy.async.global;" ::: "memory");
      asm volatile("bar.sync 3, 96;" ::: "memory");
      if (warp == 0) {
        asm volatile("{\n.reg .pred e;\nelect.sync _|e, 0xffffffff;\n@e red.release.gpu.global.inc.u32 [%0], 0xffffffff;\n}\n"
                     ::"l"(wprep + OFF_SYNC + (blockIdx.x & 3) * 128) : "memory");
        __syncwarp();
      }
    }
    if (warp == 5) { spin_until(TSP); load_in(0, 0, &tmx64); }
  }
  if (warp == 5) { spin_until(TS1); load_in(1, 0, &tmx64); }

  uint32_t AD[5];
  AD[4] = __shfl_sync(0xffffffffu, tid >= 128 ? IN0_WG1 : 0u, 0);
  {
    const uint32_t lin0 = sb + OFF_IN + ((((lane >> 3) ^ lane) & 1) ? PLANE : 0) + wi * 2 * ROWP + (lane & 7) * 64 + (lane >> 4) * 16;
#pragma unroll
    for (int n = 0; n < 4; n++) {
      const uint32_t l = lin0 + 64 * n;
      AD[n] = l ^ ((l >> 3) & 0x30u) ^ (wg * 32);
      asm volatile("" : "+r"(AD[n]));
    }
  }
  Ctx cx;
  cx.sb = sb;
  cx.d0 = ((512u >> 4) << 16) | ((sb & 0x3FFFF) >> 4);
  cx.dres = cx.d0 + (wg ? (5 * CHK) >> 4 : 0);
  cx.dstep = wg ? 0u - (CHK >> 4) : (CHK >> 4);
  cx.wg = wg;
  cx.odd = (lane >> 2) & 1;

  float acc[4][48];
  const uint32_t baddr = sb + OFF_BIAS + warp * 192 + (lane & 3) * 16;
#pragma unroll
  for (int m = 0; m < 3; m++) {
#pragma unroll
    for (int jj = 0; jj < 4; jj++) {
      const int i0 = 4 * (4 * m + jj);
      const uint32_t v = b0[m][jj] = bop<false>(b0[m][jj], b0[m][jj]);
      acc[1][i0] = vlo<0>(v); acc[1][i0 + 1] = vhi<0>(v); acc[1][i0 + 2] = vlo<1>(v); acc[1][i0 + 3] = vhi<1>(v);
    }
    if (lane < 4)
      asm volatile("st.shared.v4.u32 [%0], {%1,%2,%3,%4};" ::"r"(baddr + m * 64), "r"(b0[m][0]), "r"(b0[m][1]), "r"(b0[m][2]), "r"(b0[m][3]) : "memory");
  }
  __syncwarp();
  for (int it = (warp + 2) & 7; it < 6 * nl; it += 8) {
    const int c = (it * 43) >> 8, r = it - 6 * c;
    mbar_wait(sb + BAR_RAW + c * 8, 0);
    prep_local(sb + c * CHK + r * 1536, lane);
    asm volatile("fence.proxy.async.shared::cta;" ::: "memory");
    __syncwarp();
    mbar_arrive1(sb + BAR_RES + c * 8);
  }
  if (wg == 1) {
    if (wi == 0) {
      const uint8_t* cp = wprep + OFF_SYNC + (lane & 3) * 128;
      for (uint32_t n = 0; !__all_sync(0xffffffffu, ready == NPREP / 4); n++) {
        asm volatile("ld.relaxed.gpu.global.u32 %0, [%1];" : "=r"(ready) : "l"(cp) : "memory");
        if (n > 400000u) __trap();
      }
      asm volatile("fence.acquire.gpu;" ::: "memory");
      asm volatile("fence.proxy.async.global;" ::: "memory");
#pragma unroll
      for (int c = 0; c < 5; c++)
        if (c >= nl) bulk_chunk(sb + c * CHK, wprep + c * CHK, sb + BAR_RES + c * 8);
      mbar_wait(sb + BAR_WE, 0);
      refill_w(0);
    } else if (wi == 1) {
      asm volatile("prefetch.tensormap [%0];" ::"l"(&tmx128) : "memory");
      spin_until(TS2);
      load_in(2, 0, &tmx64);
      mbar_wait(sb + BAR_INE, 0);
      load_in(0, 1, &tmx64);
      mbar_wait(sb + BAR_INE + 8, 0);
      load_in(1, 1, &tmx128);
    } else if (wi == 2) {
      mbar_wait(sb + BAR_RES + 32, 0);
      uint32_t old = 0;
      if (lane == 0) asm volatile("atom.relaxed.gpu.global.inc.u32 %0, [%1], %2;" : "=r"(old) : "l"(wprep + OFF_SYNC + 512), "n"(NCTA - 1) : "memory");
      if (__shfl_sync(0xffffffffu, old, 0) == NCTA - 1 && lane < 4)
        asm volatile("st.relaxed.gpu.global.u32 [%0], 0;" ::"l"(wprep + OFF_SYNC + lane * 128) : "memory");
      __syncwarp();
    }
#pragma unroll
    for (int c = 1; c < 5; c++) mbar_wait(sb + BAR_RES + c * 8, 0);
    mbar_wait(sb + BAR_GO, 0);
  }
  mbar_wait(sb + BAR_RES, 0);
  mbar_wait(sb + BAR_INF + wg * 24, 0);

  for (int u = wg;; u += 2) {
    uint8_t* op[2];
    uint32_t bb[4];
    cx.first = (u == 0);
    {
      uint32_t D0[8], D1[8], D2[8];
      ldraw<0, 0, 0>(AD, D0); ldraw<0, 2, 0>(AD, D2); ldraw<0, 0, 1>(AD, D0); ldraw<0, 2, 1>(AD, D2);
      sfence();
      chunk<0>(cx, acc, D0, D1, D2, AD);
      chunk<1>(cx, acc, D0, D1, D2, AD);
      chunk<2>(cx, acc, D0, D1, D2, AD);
      chunk<3>(cx, acc, D0, D1, D2, AD);
      chunk<4>(cx, acc, D0, D1, D2, AD);
      chunk<5>(cx, acc, D0, D1, D2, AD);
    }
    {
      int x0, y0;
      unit_xy(u, x0, y0);
      const uint32_t ooff = (uint32_t)(((y0 + wi * 2) * IMG + x0 + 2 * (lane >> 2)) * (CH * 2) + (lane & 3) * 16);
      op[0] = reinterpret_cast<uint8_t*>(out) + (ooff + (cx.odd ? 192u : 0u));
      op[1] = reinterpret_cast<uint8_t*>(out) + (ooff + (cx.odd ? 0u : 192u));
    }
    wg_wait<3>();
    acc_fence(acc[0]); acc_fence(acc[1]); acc_fence(acc[2]);
    if (u == ulast) {
      piece<0, 0, 0, false>(acc, bb, op); piece<1, 0, 0, false>(acc, bb, op); piece<2, 0, 0, false>(acc, bb, op);
      piece<0, 1, 0, false>(acc, bb, op); piece<1, 1, 0, false>(acc, bb, op); piece<2, 1, 0, false>(acc, bb, op);
      wg_wait<0>();
      acc_fence(acc[3]);
      piece<0, 0, 1, false>(acc, bb, op); piece<1, 0, 1, false>(acc, bb, op); piece<2, 0, 1, false>(acc, bb, op);
      piece<0, 1, 1, false>(acc, bb, op); piece<1, 1, 1, false>(acc, bb, op); piece<2, 1, 1, false>(acc, bb, op);
      break;
    }
    const int un = u + 2;
    const bool more = un <= ulast;
    const uint32_t po = wg ^ 1;
    piece<0, 0, 0, true>(acc, bb, op);
    wg_wait<0>();
    acc_fence(acc[3]);
    lds128(baddr, bb);
    asm volatile("bar.sync %0, 128;" ::"r"(4 + wg) : "memory");
    if (wi == 1) load_in(2, u + 1, &tmx128);
    sfence();
    piece<0, 0, 1, true>(acc, bb, op); piece<0, 1, 0, true>(acc, bb, op);
    if (wi == 3 && u < LEAD0 && more) load_in(0, un, &tmx256);
    piece<0, 1, 1, true>(acc, bb, op);
    lds128(baddr + 64, bb);
    piece<1, 0, 0, true>(acc, bb, op);
    if (wi == 2) { mbar_wait(sb + BAR_WE, po); refill_w(po); }
    piece<1, 0, 1, true>(acc, bb, op); piece<1, 1, 0, true>(acc, bb, op); piece<1, 1, 1, true>(acc, bb, op);
    if (wi == 0 && more) { mbar_wait(sb + BAR_INE + 8, po); load_in(1, un, &tmx128); }
    lds128(baddr + 128, bb);
    if (wi == 3 && u + 1 >= LEAD0 && u + 3 <= ulast) { mbar_wait(sb + BAR_INE, po); load_in(0, u + 3, &tmx256); }
    piece<2, 0, 0, true>(acc, bb, op); piece<2, 0, 1, true>(acc, bb, op);
    piece<2, 1, 0, true>(acc, bb, op); piece<2, 1, 1, true>(acc, bb, op);
    if (!more) break;
    mbar_wait(sb + BAR_INF + wg * 24, (un >> 1) & 1);
    mbar_wait(sb + BAR_GO, po);
  }
}

typedef CUresult (*EncodeFn)(CUtensorMap*, CUtensorMapDataType, cuuint32_t, void*, const cuuint64_t*, const cuuint64_t*, const cuuint32_t*,
                             const cuuint32_t*, CUtensorMapInterleave, CUtensorMapSwizzle, CUtensorMapL2promotion, CUtensorMapFloatOOBfill);

}

extern "C" void kernel_launch(void* const* d_in, const int* in_sizes, int n_in, void* d_out, int out_size) {
  const __nv_bfloat16* x = (const __nv_bfloat16*)d_in[0];
  const __nv_bfloat16* w = (const __nv_bfloat16*)d_in[1];
  const __nv_bfloat16* b = (const __nv_bfloat16*)d_in[2];
  __nv_bfloat16* out = (__nv_bfloat16*)d_out;

  static EncodeFn enc = nullptr;
  static void* wp = nullptr;
  if (!enc) {
    cudaGetSymbolAddress(&wp, g_wprep);
    cudaDriverEntryPointQueryResult qr;
    cudaGetDriverEntryPoint("cuTensorMapEncodeTiled", (void**)&enc, cudaEnableDefault, &qr);
    cudaFuncSetAttribute(conv_kernel, cudaFuncAttributeMaxDynamicSharedMemorySize, SMEM_BYTES);
  }
  CUtensorMap tmx[3], tmw;
  const cuuint64_t dims[4] = {(cuuint64_t)CH, (cuuint64_t)(IMG / 2), 2, (cuuint64_t)IMG};
  const cuuint64_t strides[3] = {(cuuint64_t)CH * 4, (cuuint64_t)CH * 2, (cuuint64_t)IMG * CH * 2};
  const cuuint32_t box[4] = {32, 9, 1, 10};
  const cuuint32_t es[4] = {1, 1, 1, 1};
  const CUtensorMapL2promotion promo[3] = {CU_TENSOR_MAP_L2_PROMOTION_L2_64B, CU_TENSOR_MAP_L2_PROMOTION_L2_128B, CU_TENSOR_MAP_L2_PROMOTION_L2_256B};
  for (int i = 0; i < 3; i++)
    enc(&tmx[i], CU_TENSOR_MAP_DATA_TYPE_BFLOAT16, 4, (void*)x, dims, strides, box, es, CU_TENSOR_MAP_INTERLEAVE_NONE, CU_TENSOR_MAP_SWIZZLE_64B,
        promo[i], CU_TENSOR_MAP_FLOAT_OOB_FILL_NONE);
  const cuuint64_t wdims[3] = {192, 12, 9};
  const cuuint64_t wstrides[2] = {1536, 18432};
  const cuuint32_t wbox[3] = {192, 2, 9};
  enc(&tmw, CU_TENSOR_MAP_DATA_TYPE_UINT64, 3, (void*)w, wdims, wstrides, wbox, es, CU_TENSOR_MAP_INTERLEAVE_NONE, CU_TENSOR_MAP_SWIZZLE_NONE,
      CU_TENSOR_MAP_L2_PROMOTION_L2_128B, CU_TENSOR_MAP_FLOAT_OOB_FILL_NONE);

  conv_kernel<<<NCTA, 256, SMEM_BYTES>>>((uint8_t*)wp, w, b, out, tmw, tmx[0], tmx[1], tmx[2]);
}
```
